```python
import torch

def _softmax(x, axis=-1):
    return torch.softmax(x, dim=axis)
def _gelu(x):
    return torch.nn.functional.gelu(x, approximate="tanh")
def _silu(x):
    return torch.nn.functional.silu(x)
def _sigmoid(x):
    return torch.sigmoid(x)
def _layernorm(x, axis=-1, eps=1e-5):
    m = x.mean(dim=axis, keepdim=True)
    v = x.var(dim=axis, keepdim=True, unbiased=False)
    return (x - m) / torch.sqrt(v + eps)
def _scatter_add(tgt, idx, src, axis=0):
    return tgt.clone().index_add_(axis, idx, src)
def _segment_sum(src, seg, n):
    out = torch.zeros((n,) + src.shape[1:], dtype=src.dtype)
    return out.index_add_(0, seg, src)
def _pad(x, pw):
    flat = tuple(v for pair in reversed(pw) for v in pair)
    return torch.nn.functional.pad(x, flat)

kernel_name = 'recurrent_scan__gqa_block_cached__glu_gated_swiglu__prompt'

def setup_inputs():

    _w = (lambda a: (lambda t: t.to(torch.bfloat16) if t.is_floating_point() else t)(torch.as_tensor(a)))
    def _A_setup():
        B, Sq, D = 1, 2048, 576
        Hq, Hkv, Sk, Dh = 32, 16, 2048, 128
        assert Hq % Hkv == 0, (Hq, Hkv)
        return {
            "x": _w((lambda *s: torch.randn(*s, dtype=torch.bfloat16) * 0.05)(B, Sq, D)),
            "k_cache": _w((lambda *s: torch.randn(*s, dtype=torch.bfloat16) * 1.6)(B, Hkv, Sk, Dh)),
            "v_cache": _w((lambda *s: torch.randn(*s, dtype=torch.bfloat16) * 1.6)(B, Hkv, Sk, Dh)),
            "wq": _w((lambda *s: torch.randn(*s, dtype=torch.bfloat16) * 1.6)(D, Hq * Dh) * (D ** -0.5)),
            "wo": _w((lambda *s: torch.randn(*s, dtype=torch.bfloat16) * 1.6)(Hq * Dh, D) * ((Hq * Dh) ** -0.5)),
        }
    _A_in = _A_setup()

    def _B_setup():
        B, S, D, F = 1, 2048, 576, 4608
        return {
            "x": _w((lambda *s: torch.randn(*s, dtype=torch.bfloat16) * 0.05)(B, S, D)),
            "w1": _w((lambda *s: torch.randn(*s, dtype=torch.bfloat16) * 0.2)(D, F) * (2.0 / D) ** 0.5),
            "w3": _w((lambda *s: torch.randn(*s, dtype=torch.bfloat16) * 0.2)(D, F) * (2.0 / D) ** 0.5),
            "w2": _w((lambda *s: torch.randn(*s, dtype=torch.bfloat16) * 0.2)(F, D) * (2.0 / F) ** 0.5),
        }
    _B_in = _B_setup()

    return {
        "A_x": _A_in["x"],
        "A_k_cache": _A_in["k_cache"],
        "A_v_cache": _A_in["v_cache"],
        "A_wq": _A_in["wq"],
        "A_wo": _A_in["wo"],
        "B_x": _B_in["x"],
        "B_w1": _B_in["w1"],
        "B_w3": _B_in["w3"],
        "B_w2": _B_in["w2"],
    }

def reference(A_x, A_k_cache, A_v_cache, A_wq, A_wo, B_x, B_w1, B_w3, B_w2):
    def _A_ref(x, k_cache, v_cache, wq, wo):
        B, Sq, D = x.shape
        Hq, Dh = 32, 128
        Hkv = k_cache.shape[1]
        rep = Hq // Hkv
        q = (lambda x, *d: x.permute(*d))((x @ wq).reshape(B, Sq, Hq, Dh), 0, 2, 1, 3)
        k = (lambda x, n, axis: torch.repeat_interleave(x, n, dim=axis))(k_cache, rep, axis=1)
        v = (lambda x, n, axis: torch.repeat_interleave(x, n, dim=axis))(v_cache, rep, axis=1)
        scores = torch.einsum("bhqd,bhkd->bhqk", q, k) * (Dh ** -0.5)
        p = _softmax(scores, axis=-1)
        o = torch.einsum("bhqk,bhkd->bhqd", p, v)
        return (lambda x, *d: x.permute(*d))(o, 0, 2, 1, 3).reshape(B, Sq, Hq * Dh) @ wo

    def _B_ref(x, w1, w3, w2):
        gate = torch.einsum("bsd,df->bsf", x, w1)
        up = torch.einsum("bsd,df->bsf", x, w3)
        h = _silu(gate) * up
        out = torch.einsum("bsf,fd->bsd", h, w2)
        return out

    x = A_x
    xn = _layernorm(x, axis=-1)
    s = _A_ref(xn, A_k_cache, A_v_cache, A_wq, A_wo)
    g = _silu(_B_ref(xn, B_w1, B_w3, B_w2))
    return x + s * g
```

```cpp
#include <cuda_runtime.h>
#include <cuda_bf16.h>
#include <cuda.h>
#include <stdint.h>
#include <string.h>

namespace {

constexpr int SEQ = 2048, DM = 576, NH = 32, DH = 128, FF = 4608;
constexpr int NSTAGE = 7, STAGE_BYTES = 32768;
constexpr int MAX_TASKS = 6;
constexpr int MAX_CLUSTERS = 66;
constexpr int NSIG = 24;
constexpr int SMEM_BYTES = NSTAGE * STAGE_BYTES + 1024 + 128 + NSIG * 16;
constexpr uint32_t SPIN_LIMIT = 1u << 21;

enum { T_END = 0, T_XW = 1, T_ATT = 2, T_D = 3, T_P = 4, T_XWU = 5 };
struct Task { uint8_t type, mp, a, b, c, d, e, f; };

struct Params {
  CUtensorMap tm_x, tm_k, tm_v, tm_wq, tm_w1, tm_w3, tm_wo, tm_w2, tm_x3;
  __nv_bfloat16* out;
  const __nv_bfloat16 *wo, *w2;
  int nctas;
  int last;
  Task tasks[MAX_CLUSTERS][MAX_TASKS];
  uint8_t horder[8][32];
  uint8_t hperm[8][32];
};

__device__ uint4 g_qo[32 * 256 * 128];
__device__ uint4 g_h[32 * 288 * 128];
__device__ uint4 g_g[32 * 3 * 16 * 128];
constexpr int FL_H = 0;
constexpr int FL_O = 16;
constexpr int FL_Q = 16 + 512;
constexpr int FL_LAUNCH = FL_Q + 512;
constexpr int FL_TOTAL = FL_LAUNCH + 4;
__device__ unsigned g_flags[FL_TOTAL];

__device__ __forceinline__ uint32_t smem_u32(const void* p) { return (uint32_t)__cvta_generic_to_shared(p); }
__device__ __forceinline__ void wg_fence() { asm volatile("wgmma.fence.sync.aligned;" ::: "memory"); }
__device__ __forceinline__ void wg_commit() { asm volatile("wgmma.commit_group.sync.aligned;" ::: "memory"); }
template <int N> __device__ __forceinline__ void wg_wait() { asm volatile("wgmma.wait_group.sync.aligned %0;" ::"n"(N) : "memory"); }
template <int N> __device__ __forceinline__ void reg_fence(float (&d)[N]) {
#pragma unroll
  for (int i = 0; i < N; i++) asm volatile("" : "+f"(d[i])::"memory");
}
__device__ __forceinline__ uint64_t mkdesc(uint32_t lo) { return ((uint64_t)(0x40000000u | (1024u >> 4)) << 32) | lo; }
__device__ __forceinline__ uint32_t desc_lo(uint32_t addr, uint32_t lbo) { return ((addr & 0x3FFFF) >> 4) | ((lbo >> 4) << 16); }

__device__ __forceinline__ void mbar_init(uint32_t bar, int cnt) { asm volatile("mbarrier.init.shared::cta.b64 [%0], %1;" ::"r"(bar), "r"(cnt) : "memory"); }
__device__ __forceinline__ bool elect_one() {
  uint32_t pred;
  asm volatile("{\n.reg .pred p;\nelect.sync _|p, 0xffffffff;\nselp.u32 %0, 1, 0, p;\n}" : "=r"(pred));
  return pred;
}
__device__ __forceinline__ void mbar_expect(uint32_t bar, int bytes) {
  asm volatile("mbarrier.arrive.expect_tx.shared::cta.b64 _, [%0], %1;" ::"r"(bar), "r"(bytes) : "memory");
}
__device__ __forceinline__ void mbar_arrive(uint32_t bar) { asm volatile("mbarrier.arrive.shared::cta.b64 _, [%0];" ::"r"(bar) : "memory"); }
__device__ __forceinline__ void mbar_arrive_cluster(uint32_t bar_cluster_addr) {
  asm volatile("mbarrier.arrive.shared::cluster.b64 _, [%0];" ::"r"(bar_cluster_addr) : "memory");
}
__device__ __forceinline__ void mbar_wait(uint32_t bar, uint32_t parity) {
  asm volatile(
      "{\n.reg .pred p;\n.reg .u32 n;\n"
      "mov.u32 n, 0;\n"
      "LOOP:\n"
      "mbarrier.try_wait.parity.shared::cta.b64 p, [%0], %1;\n"
      "@p bra DONE;\n"
      "add.u32 n, n, 1;\n"
      "setp.gt.u32 p, n, %2;\n"
      "@p trap;\n"
      "bra LOOP;\n"
      "DONE:\n}" ::"r"(bar), "r"(parity), "n"(SPIN_LIMIT) : "memory");
}
__device__ __forceinline__ void mbar_wait_fast(uint32_t bar, uint32_t parity) {
  asm volatile(
      "{\n.reg .pred p;\n"
      "LOOP:\n"
      "mbarrier.try_wait.parity.shared::cta.b64 p, [%0], %1;\n"
      "@!p bra LOOP;\n}" ::"r"(bar), "r"(parity) : "memory");
}
#define UNLIKELY(x) __builtin_expect(!!(x), 0)
__device__ __forceinline__ void sched_boundary(uint32_t z) {
  asm volatile("{\n.reg .pred p;\nsetp.eq.u32 p, %0, 0;\n@p bra SKIP;\ntrap;\nSKIP:\n}" ::"r"(z) : "memory");
}
__device__ __forceinline__ uint32_t mapa(uint32_t addr, uint32_t rank) {
  uint32_t r;
  asm("mapa.shared::cluster.u32 %0, %1, %2;" : "=r"(r) : "r"(addr), "r"(rank));
  return r;
}
__device__ __forceinline__ void cluster_sync() {
  asm volatile("barrier.cluster.arrive.relaxed.aligned;\nbarrier.cluster.wait.aligned;" ::: "memory");
}
__device__ __forceinline__ void tma2d(uint32_t dst, const CUtensorMap* tm, int c0, int c1, uint32_t bar) {
  asm volatile("cp.async.bulk.tensor.2d.shared::cluster.global.mbarrier::complete_tx::bytes [%0], [%1, {%3, %4}], [%2];"
               ::"r"(dst), "l"(tm), "r"(bar), "r"(c0), "r"(c1) : "memory");
}
__device__ __forceinline__ void tma2d_mc(uint32_t dst, const CUtensorMap* tm, int c0, int c1, uint32_t bar) {
  asm volatile("cp.async.bulk.tensor.2d.shared::cluster.global.mbarrier::complete_tx::bytes.multicast::cluster [%0], [%1, {%3, %4}], [%2], %5;"
               ::"r"(dst), "l"(tm), "r"(bar), "r"(c0), "r"(c1), "h"((uint16_t)3) : "memory");
}
__device__ __forceinline__ void tma3d_mc(uint32_t dst, const CUtensorMap* tm, int c0, int c1, int c2, uint32_t bar) {
  asm volatile("cp.async.bulk.tensor.3d.shared::cluster.global.mbarrier::complete_tx::bytes.multicast::cluster [%0], [%1, {%3, %4, %5}], [%2], %6;"
               ::"r"(dst), "l"(tm), "r"(bar), "r"(c0), "r"(c1), "r"(c2), "h"((uint16_t)3) : "memory");
}
__device__ __forceinline__ void tma3d(uint32_t dst, const CUtensorMap* tm, int c0, int c1, int c2, uint32_t bar) {
  asm volatile("cp.async.bulk.tensor.3d.shared::cluster.global.mbarrier::complete_tx::bytes [%0], [%1, {%3, %4, %5}], [%2];"
               ::"r"(dst), "l"(tm), "r"(bar), "r"(c0), "r"(c1), "r"(c2) : "memory");
}
__device__ __forceinline__ void l2_prefetch(const void* src, uint32_t bytes) {
  asm volatile("cp.async.bulk.prefetch.L2.global [%0], %1;" ::"l"(src), "r"(bytes) : "memory");
}
__device__ __forceinline__ void bulk_load(uint32_t dst, const void* src, uint32_t bytes, uint32_t bar) {
  asm volatile("cp.async.bulk.shared::cluster.global.mbarrier::complete_tx::bytes [%0], [%1], %2, [%3];" ::"r"(dst), "l"(src), "r"(bytes), "r"(bar)
               : "memory");
}
__device__ __forceinline__ void bar_sync(int id, int n) { asm volatile("bar.sync %0, %1;" ::"r"(id), "r"(n) : "memory"); }
__device__ __forceinline__ void bar_arrive(int id, int n) { asm volatile("bar.arrive %0, %1;" ::"r"(id), "r"(n) : "memory"); }
__device__ __forceinline__ float ex2(float x) { float y; asm("ex2.approx.ftz.f32 %0, %1;" : "=f"(y) : "f"(x)); return y; }
__device__ __forceinline__ float rcp(float x) { float y; asm("rcp.approx.ftz.f32 %0, %1;" : "=f"(y) : "f"(x)); return y; }
__device__ __forceinline__ uint32_t pack2(float lo, float hi) {
  uint32_t r;
  asm("cvt.rn.bf16x2.f32 %0, %1, %2;" : "=r"(r) : "f"(hi), "f"(lo));
  return r;
}
__device__ __forceinline__ float silu(float g) { return g * rcp(1.0f + ex2(g * -1.4426950408889634f)); }
__device__ __forceinline__ void st_tagged(void* p, uint32_t a, uint32_t b, uint32_t c, uint32_t tag) {
  asm volatile("{\n.reg .b128 v;\nmov.b128 v, {%1, %2, %3, %4};\nst.relaxed.gpu.global.b128 [%0], v;\n}" ::"l"(p), "r"(a), "r"(b), "r"(c), "r"(tag) : "memory");
}
__device__ __forceinline__ void ld_tagged(const void* p, uint32_t& a, uint32_t& b, uint32_t& c, uint32_t& tag) {
  asm volatile("{\n.reg .b128 v;\nld.relaxed.gpu.global.b128 v, [%4];\nmov.b128 {%0, %1, %2, %3}, v;\n}" : "=r"(a), "=r"(b), "=r"(c), "=r"(tag) : "l"(p) : "memory");
}
__device__ __forceinline__ void stg_v4(void* p, uint32_t a, uint32_t b, uint32_t c, uint32_t d) {
  asm volatile("st.global.v4.u32 [%0], {%1, %2, %3, %4};" ::"l"(p), "r"(a), "r"(b), "r"(c), "r"(d) : "memory");
}
__device__ __forceinline__ unsigned ld_acquire(const unsigned* p) {
  unsigned v;
  asm volatile("ld.acquire.gpu.global.u32 %0, [%1];" : "=r"(v) : "l"(p) : "memory");
  return v;
}
__device__ __forceinline__ void flag_wait(const unsigned* p, unsigned target) {
  uint32_t n = 0;
  while (ld_acquire(p) < target) {
    if (++n > SPIN_LIMIT) asm volatile("trap;");
  }
}
__device__ __forceinline__ void mma16816(float (&c)[4], uint32_t a0, uint32_t a1, uint32_t a2, uint32_t a3, uint32_t b0, uint32_t b1) {
  asm volatile("mma.sync.aligned.m16n8k16.row.col.f32.bf16.bf16.f32 {%0,%1,%2,%3}, {%4,%5,%6,%7}, {%8,%9}, {%0,%1,%2,%3};"
               : "+f"(c[0]), "+f"(c[1]), "+f"(c[2]), "+f"(c[3]) : "r"(a0), "r"(a1), "r"(a2), "r"(a3), "r"(b0), "r"(b1));
}

template <int TB>
__device__ __forceinline__ void wgmma_rs_n128(float (&d)[64], uint32_t a0, uint32_t a1, uint32_t a2, uint32_t a3, uint64_t descB, int scaleD) {
  asm volatile("{\n.reg .pred p;\nsetp.ne.b32 p, %69, 0;\n"
    "wgmma.mma_async.sync.aligned.m64n128k16.f32.bf16.bf16 "
    "{%0, %1, %2, %3, %4, %5, %6, %7, %8, %9, %10, %11, %12, %13, %14, %15, %16, %17, %18, %19, %20, %21, %22, %23, %24, %25, %26, %27, %28, %29, %30, %31, %32, %33, %34, %35, %36, %37, %38, %39, %40, %41, %42, %43, %44, %45, %46, %47, %48, %49, %50, %51, %52, %53, %54, %55, %56, %57, %58, %59, %60, %61, %62, %63}, "
    "{%64, %65, %66, %67}, %68, p, 1, 1, %70;\n}\n"
    : "+f"(d[0]), "+f"(d[1]), "+f"(d[2]), "+f"(d[3]), "+f"(d[4]), "+f"(d[5]), "+f"(d[6]), "+f"(d[7]), "+f"(d[8]), "+f"(d[9]), "+f"(d[10]), "+f"(d[11]), "+f"(d[12]), "+f"(d[13]), "+f"(d[14]), "+f"(d[15]), "+f"(d[16]), "+f"(d[17]), "+f"(d[18]), "+f"(d[19]), "+f"(d[20]), "+f"(d[21]), "+f"(d[22]), "+f"(d[23]), "+f"(d[24]), "+f"(d[25]), "+f"(d[26]), "+f"(d[27]), "+f"(d[28]), "+f"(d[29]), "+f"(d[30]), "+f"(d[31]), "+f"(d[32]), "+f"(d[33]), "+f"(d[34]), "+f"(d[35]), "+f"(d[36]), "+f"(d[37]), "+f"(d[38]), "+f"(d[39]), "+f"(d[40]), "+f"(d[41]), "+f"(d[42]), "+f"(d[43]), "+f"(d[44]), "+f"(d[45]), "+f"(d[46]), "+f"(d[47]), "+f"(d[48]), "+f"(d[49]), "+f"(d[50]), "+f"(d[51]), "+f"(d[52]), "+f"(d[53]), "+f"(d[54]), "+f"(d[55]), "+f"(d[56]), "+f"(d[57]), "+f"(d[58]), "+f"(d[59]), "+f"(d[60]), "+f"(d[61]), "+f"(d[62]), "+f"(d[63])
    : "r"(a0), "r"(a1), "r"(a2), "r"(a3), "l"(descB), "r"(scaleD), "n"(TB));
}

template <int TB>
__device__ __forceinline__ void wgmma_rs_n192(float (&d)[96], uint32_t a0, uint32_t a1, uint32_t a2, uint32_t a3, uint64_t descB, int scaleD) {
  asm volatile("{\n.reg .pred p;\nsetp.ne.b32 p, %101, 0;\n"
    "wgmma.mma_async.sync.aligned.m64n192k16.f32.bf16.bf16 "
    "{%0, %1, %2, %3, %4, %5, %6, %7, %8, %9, %10, %11, %12, %13, %14, %15, %16, %17, %18, %19, %20, %21, %22, %23, %24, %25, %26, %27, %28, %29, %30, %31, %32, %33, %34, %35, %36, %37, %38, %39, %40, %41, %42, %43, %44, %45, %46, %47, %48, %49, %50, %51, %52, %53, %54, %55, %56, %57, %58, %59, %60, %61, %62, %63, %64, %65, %66, %67, %68, %69, %70, %71, %72, %73, %74, %75, %76, %77, %78, %79, %80, %81, %82, %83, %84, %85, %86, %87, %88, %89, %90, %91, %92, %93, %94, %95}, "
    "{%96, %97, %98, %99}, %100, p, 1, 1, %102;\n}\n"
    : "+f"(d[0]), "+f"(d[1]), "+f"(d[2]), "+f"(d[3]), "+f"(d[4]), "+f"(d[5]), "+f"(d[6]), "+f"(d[7]), "+f"(d[8]), "+f"(d[9]), "+f"(d[10]), "+f"(d[11]), "+f"(d[12]), "+f"(d[13]), "+f"(d[14]), "+f"(d[15]), "+f"(d[16]), "+f"(d[17]), "+f"(d[18]), "+f"(d[19]), "+f"(d[20]), "+f"(d[21]), "+f"(d[22]), "+f"(d[23]), "+f"(d[24]), "+f"(d[25]), "+f"(d[26]), "+f"(d[27]), "+f"(d[28]), "+f"(d[29]), "+f"(d[30]), "+f"(d[31]), "+f"(d[32]), "+f"(d[33]), "+f"(d[34]), "+f"(d[35]), "+f"(d[36]), "+f"(d[37]), "+f"(d[38]), "+f"(d[39]), "+f"(d[40]), "+f"(d[41]), "+f"(d[42]), "+f"(d[43]), "+f"(d[44]), "+f"(d[45]), "+f"(d[46]), "+f"(d[47]), "+f"(d[48]), "+f"(d[49]), "+f"(d[50]), "+f"(d[51]), "+f"(d[52]), "+f"(d[53]), "+f"(d[54]), "+f"(d[55]), "+f"(d[56]), "+f"(d[57]), "+f"(d[58]), "+f"(d[59]), "+f"(d[60]), "+f"(d[61]), "+f"(d[62]), "+f"(d[63]), "+f"(d[64]), "+f"(d[65]), "+f"(d[66]), "+f"(d[67]), "+f"(d[68]), "+f"(d[69]), "+f"(d[70]), "+f"(d[71]), "+f"(d[72]), "+f"(d[73]), "+f"(d[74]), "+f"(d[75]), "+f"(d[76]), "+f"(d[77]), "+f"(d[78]), "+f"(d[79]), "+f"(d[80]), "+f"(d[81]), "+f"(d[82]), "+f"(d[83]), "+f"(d[84]), "+f"(d[85]), "+f"(d[86]), "+f"(d[87]), "+f"(d[88]), "+f"(d[89]), "+f"(d[90]), "+f"(d[91]), "+f"(d[92]), "+f"(d[93]), "+f"(d[94]), "+f"(d[95])
    : "r"(a0), "r"(a1), "r"(a2), "r"(a3), "l"(descB), "r"(scaleD), "n"(TB));
}

static const uint8_t SCHED[66][6][6] = {
  {{1,0,0,0,0,5}, {2,0,0,6,0,0}, {0,0,0,0,0,0}, {0,0,0,0,0,0}, {0,0,0,0,0,0}, {0,0,0,0,0,0}},
  {{1,0,0,5,5,5}, {2,0,6,4,0,0}, {4,0,0,0,0,0}, {0,0,0,0,0,0}, {0,0,0,0,0,0}, {0,0,0,0,0,0}},
  {{1,0,5,6,10,4}, {2,0,10,4,0,0}, {4,0,1,0,0,0}, {0,0,0,0,0,0}, {0,0,0,0,0,0}, {0,0,0,0,0,0}},
  {{1,0,11,6,14,4}, {2,0,14,4,0,0}, {4,0,2,0,0,0}, {0,0,0,0,0,0}, {0,0,0,0,0,0}, {0,0,0,0,0,0}},
  {{1,0,17,12,18,3}, {2,0,18,3,0,0}, {3,0,0,0,0,0}, {0,0,0,0,0,0}, {0,0,0,0,0,0}, {0,0,0,0,0,0}},
  {{1,1,0,0,0,5}, {2,1,0,6,0,0}, {0,0,0,0,0,0}, {0,0,0,0,0,0}, {0,0,0,0,0,0}, {0,0,0,0,0,0}},
  {{1,2,0,0,0,2}, {5,1,68,2,0,0}, {2,2,0,6,0,0}, {0,0,0,0,0,0}, {0,0,0,0,0,0}, {0,0,0,0,0,0}},
  {{1,3,0,0,0,2}, {5,0,68,2,0,0}, {2,3,0,6,0,0}, {0,0,0,0,0,0}, {0,0,0,0,0,0}, {0,0,0,0,0,0}},
  {{1,4,0,0,0,5}, {2,4,0,6,0,0}, {0,0,0,0,0,0}, {0,0,0,0,0,0}, {0,0,0,0,0,0}, {0,0,0,0,0,0}},
  {{1,5,0,0,0,5}, {2,5,0,6,0,0}, {0,0,0,0,0,0}, {0,0,0,0,0,0}, {0,0,0,0,0,0}, {0,0,0,0,0,0}},
  {{1,6,0,0,0,2}, {5,5,68,2,0,0}, {2,6,0,6,0,0}, {0,0,0,0,0,0}, {0,0,0,0,0,0}, {0,0,0,0,0,0}},
  {{1,7,0,0,0,2}, {5,4,68,2,0,0}, {2,7,0,6,0,0}, {0,0,0,0,0,0}, {0,0,0,0,0,0}, {0,0,0,0,0,0}},
  {{1,0,29,12,21,3}, {2,0,21,3,0,0}, {3,0,1,0,0,0}, {0,0,0,0,0,0}, {0,0,0,0,0,0}, {0,0,0,0,0,0}},
  {{1,1,0,5,5,5}, {2,1,6,4,0,0}, {4,1,0,0,0,0}, {0,0,0,0,0,0}, {0,0,0,0,0,0}, {0,0,0,0,0,0}},
  {{1,2,0,2,2,8}, {2,2,6,4,0,0}, {4,2,0,0,0,0}, {0,0,0,0,0,0}, {0,0,0,0,0,0}, {0,0,0,0,0,0}},
  {{1,3,0,2,2,8}, {2,3,6,4,0,0}, {4,3,0,0,0,0}, {0,0,0,0,0,0}, {0,0,0,0,0,0}, {0,0,0,0,0,0}},
  {{1,4,0,5,5,5}, {2,4,6,4,0,0}, {4,4,0,0,0,0}, {0,0,0,0,0,0}, {0,0,0,0,0,0}, {0,0,0,0,0,0}},
  {{1,5,0,5,5,5}, {2,5,6,4,0,0}, {4,5,0,0,0,0}, {0,0,0,0,0,0}, {0,0,0,0,0,0}, {0,0,0,0,0,0}},
  {{1,6,0,2,2,8}, {2,6,6,4,0,0}, {4,6,0,0,0,0}, {0,0,0,0,0,0}, {0,0,0,0,0,0}, {0,0,0,0,0,0}},
  {{1,7,0,2,2,8}, {2,7,6,4,0,0}, {4,7,0,0,0,0}, {0,0,0,0,0,0}, {0,0,0,0,0,0}, {0,0,0,0,0,0}},
  {{1,0,41,12,24,3}, {2,0,24,3,0,0}, {3,0,2,0,0,0}, {0,0,0,0,0,0}, {0,0,0,0,0,0}, {0,0,0,0,0,0}},
  {{1,1,5,6,10,4}, {2,1,10,4,0,0}, {4,1,1,0,0,0}, {0,0,0,0,0,0}, {0,0,0,0,0,0}, {0,0,0,0,0,0}},
  {{1,2,2,6,10,4}, {2,2,10,4,0,0}, {4,2,1,0,0,0}, {0,0,0,0,0,0}, {0,0,0,0,0,0}, {0,0,0,0,0,0}},
  {{1,3,2,6,10,4}, {2,3,10,4,0,0}, {4,3,1,0,0,0}, {0,0,0,0,0,0}, {0,0,0,0,0,0}, {0,0,0,0,0,0}},
  {{1,4,5,6,10,4}, {2,4,10,4,0,0}, {4,4,1,0,0,0}, {0,0,0,0,0,0}, {0,0,0,0,0,0}, {0,0,0,0,0,0}},
  {{1,5,5,6,10,4}, {2,5,10,4,0,0}, {4,5,1,0,0,0}, {0,0,0,0,0,0}, {0,0,0,0,0,0}, {0,0,0,0,0,0}},
  {{1,6,2,6,10,4}, {2,6,10,4,0,0}, {4,6,1,0,0,0}, {0,0,0,0,0,0}, {0,0,0,0,0,0}, {0,0,0,0,0,0}},
  {{1,7,2,6,10,4}, {2,7,10,4,0,0}, {4,7,1,0,0,0}, {0,0,0,0,0,0}, {0,0,0,0,0,0}, {0,0,0,0,0,0}},
  {{1,0,53,15,27,5}, {2,0,27,4,0,0}, {0,0,0,0,0,0}, {0,0,0,0,0,0}, {0,0,0,0,0,0}, {0,0,0,0,0,0}},
  {{1,1,11,6,14,4}, {2,1,14,4,0,0}, {4,1,2,0,0,0}, {0,0,0,0,0,0}, {0,0,0,0,0,0}, {0,0,0,0,0,0}},
  {{1,2,8,6,14,4}, {2,2,14,4,0,0}, {4,2,2,0,0,0}, {0,0,0,0,0,0}, {0,0,0,0,0,0}, {0,0,0,0,0,0}},
  {{1,3,8,6,14,4}, {2,3,14,4,0,0}, {4,3,2,0,0,0}, {0,0,0,0,0,0}, {0,0,0,0,0,0}, {0,0,0,0,0,0}},
  {{1,4,11,6,14,4}, {2,4,14,4,0,0}, {4,4,2,0,0,0}, {0,0,0,0,0,0}, {0,0,0,0,0,0}, {0,0,0,0,0,0}},
  {{1,5,11,6,14,4}, {2,5,14,4,0,0}, {4,5,2,0,0,0}, {0,0,0,0,0,0}, {0,0,0,0,0,0}, {0,0,0,0,0,0}},
  {{1,6,8,6,14,4}, {2,6,14,4,0,0}, {4,6,2,0,0,0}, {0,0,0,0,0,0}, {0,0,0,0,0,0}, {0,0,0,0,0,0}},
  {{1,7,8,6,14,4}, {2,7,14,4,0,0}, {4,7,2,0,0,0}, {0,0,0,0,0,0}, {0,0,0,0,0,0}, {0,0,0,0,0,0}},
  {{1,1,17,12,18,3}, {2,1,18,3,0,0}, {3,1,0,0,0,0}, {0,0,0,0,0,0}, {0,0,0,0,0,0}, {0,0,0,0,0,0}},
  {{1,2,14,12,18,3}, {2,2,18,3,0,0}, {3,2,0,0,0,0}, {0,0,0,0,0,0}, {0,0,0,0,0,0}, {0,0,0,0,0,0}},
  {{1,3,14,12,18,3}, {2,3,18,3,0,0}, {3,3,0,0,0,0}, {0,0,0,0,0,0}, {0,0,0,0,0,0}, {0,0,0,0,0,0}},
  {{1,4,17,12,18,3}, {2,4,18,3,0,0}, {3,4,0,0,0,0}, {0,0,0,0,0,0}, {0,0,0,0,0,0}, {0,0,0,0,0,0}},
  {{1,5,17,12,18,3}, {2,5,18,3,0,0}, {3,5,0,0,0,0}, {0,0,0,0,0,0}, {0,0,0,0,0,0}, {0,0,0,0,0,0}},
  {{1,6,14,12,18,3}, {2,6,18,3,0,0}, {3,6,0,0,0,0}, {0,0,0,0,0,0}, {0,0,0,0,0,0}, {0,0,0,0,0,0}},
  {{1,7,14,12,18,3}, {2,7,18,3,0,0}, {3,7,0,0,0,0}, {0,0,0,0,0,0}, {0,0,0,0,0,0}, {0,0,0,0,0,0}},
  {{1,1,29,12,21,3}, {2,1,21,3,0,0}, {3,1,1,0,0,0}, {0,0,0,0,0,0}, {0,0,0,0,0,0}, {0,0,0,0,0,0}},
  {{1,2,26,12,21,3}, {2,2,21,3,0,0}, {3,2,1,0,0,0}, {0,0,0,0,0,0}, {0,0,0,0,0,0}, {0,0,0,0,0,0}},
  {{1,3,26,12,21,3}, {2,3,21,3,0,0}, {3,3,1,0,0,0}, {0,0,0,0,0,0}, {0,0,0,0,0,0}, {0,0,0,0,0,0}},
  {{1,4,29,12,21,3}, {2,4,21,3,0,0}, {3,4,1,0,0,0}, {0,0,0,0,0,0}, {0,0,0,0,0,0}, {0,0,0,0,0,0}},
  {{1,5,29,12,21,3}, {2,5,21,3,0,0}, {3,5,1,0,0,0}, {0,0,0,0,0,0}, {0,0,0,0,0,0}, {0,0,0,0,0,0}},
  {{1,6,26,12,21,3}, {2,6,21,3,0,0}, {3,6,1,0,0,0}, {0,0,0,0,0,0}, {0,0,0,0,0,0}, {0,0,0,0,0,0}},
  {{1,7,26,12,21,3}, {2,7,21,3,0,0}, {3,7,1,0,0,0}, {0,0,0,0,0,0}, {0,0,0,0,0,0}, {0,0,0,0,0,0}},
  {{1,1,41,12,24,3}, {2,1,24,3,0,0}, {3,1,2,0,0,0}, {0,0,0,0,0,0}, {0,0,0,0,0,0}, {0,0,0,0,0,0}},
  {{1,2,38,12,24,3}, {2,2,24,3,0,0}, {3,2,2,0,0,0}, {0,0,0,0,0,0}, {0,0,0,0,0,0}, {0,0,0,0,0,0}},
  {{1,3,38,12,24,3}, {2,3,24,3,0,0}, {3,3,2,0,0,0}, {0,0,0,0,0,0}, {0,0,0,0,0,0}, {0,0,0,0,0,0}},
  {{1,4,41,12,24,3}, {2,4,24,3,0,0}, {3,4,2,0,0,0}, {0,0,0,0,0,0}, {0,0,0,0,0,0}, {0,0,0,0,0,0}},
  {{1,5,41,12,24,3}, {2,5,24,3,0,0}, {3,5,2,0,0,0}, {0,0,0,0,0,0}, {0,0,0,0,0,0}, {0,0,0,0,0,0}},
  {{1,6,38,12,24,3}, {2,6,24,3,0,0}, {3,6,2,0,0,0}, {0,0,0,0,0,0}, {0,0,0,0,0,0}, {0,0,0,0,0,0}},
  {{1,7,38,12,24,3}, {2,7,24,3,0,0}, {3,7,2,0,0,0}, {0,0,0,0,0,0}, {0,0,0,0,0,0}, {0,0,0,0,0,0}},
  {{1,1,53,15,27,5}, {2,1,27,4,0,0}, {0,0,0,0,0,0}, {0,0,0,0,0,0}, {0,0,0,0,0,0}, {0,0,0,0,0,0}},
  {{1,2,50,22,27,5}, {2,2,27,3,0,0}, {0,0,0,0,0,0}, {0,0,0,0,0,0}, {0,0,0,0,0,0}, {0,0,0,0,0,0}},
  {{1,3,50,22,27,5}, {2,3,27,3,0,0}, {0,0,0,0,0,0}, {0,0,0,0,0,0}, {0,0,0,0,0,0}, {0,0,0,0,0,0}},
  {{1,4,53,15,27,5}, {2,4,27,4,0,0}, {0,0,0,0,0,0}, {0,0,0,0,0,0}, {0,0,0,0,0,0}, {0,0,0,0,0,0}},
  {{1,5,53,15,27,5}, {2,5,27,4,0,0}, {0,0,0,0,0,0}, {0,0,0,0,0,0}, {0,0,0,0,0,0}, {0,0,0,0,0,0}},
  {{1,6,50,22,27,5}, {2,6,27,3,0,0}, {0,0,0,0,0,0}, {0,0,0,0,0,0}, {0,0,0,0,0,0}, {0,0,0,0,0,0}},
  {{1,7,50,22,27,5}, {2,7,27,3,0,0}, {0,0,0,0,0,0}, {0,0,0,0,0,0}, {0,0,0,0,0,0}, {0,0,0,0,0,0}},
  {{5,0,70,2,0,0}, {5,1,70,2,0,0}, {2,2,30,2,0,0}, {2,0,31,1,0,0}, {2,1,31,1,0,0}, {2,3,30,2,0,0}},
  {{5,4,70,2,0,0}, {5,5,70,2,0,0}, {2,6,30,2,0,0}, {2,4,31,1,0,0}, {2,5,31,1,0,0}, {2,7,30,2,0,0}}};
static const uint8_t HORDER[8][32] = {
  {28,3,16,12,8,25,22,19,27,2,31,15,11,7,24,21,18,1,14,10,6,0,20,23,26,9,13,17,4,29,5,30},
  {28,31,3,16,12,8,25,22,19,27,2,15,11,7,24,21,18,1,14,10,6,0,20,23,26,9,13,17,4,29,5,30},
  {27,3,16,12,8,25,22,19,2,15,11,7,24,21,18,31,1,14,10,6,30,0,20,23,26,9,13,17,4,28,5,29},
  {23,20,27,3,16,12,8,25,22,19,2,15,11,7,24,21,18,1,14,10,6,0,26,9,13,17,4,28,30,5,29,31},
  {28,3,16,12,8,25,22,19,27,2,31,15,11,7,24,21,18,1,14,10,6,0,20,23,26,9,13,17,4,29,5,30},
  {28,31,3,16,12,8,25,22,19,27,2,15,11,7,24,21,18,1,14,10,6,0,20,23,26,9,13,17,4,29,5,30},
  {27,3,16,12,8,25,22,19,2,15,11,7,24,21,18,31,1,14,10,6,30,0,20,23,26,9,13,17,4,28,5,29},
  {23,20,27,3,16,12,8,25,22,19,2,15,11,7,24,21,18,1,14,10,6,0,26,9,13,17,4,28,30,5,29,31}};
static const uint8_t HPERM[8][32] = {
  {0,4,12,20,28,30,1,8,17,25,2,9,18,26,3,10,19,27,5,14,22,6,15,23,7,16,24,13,21,29,31,11},
  {0,4,11,19,28,30,1,8,16,25,2,9,17,26,3,10,18,27,5,13,22,6,14,23,7,15,24,12,21,29,31,20},
  {0,5,13,20,28,30,2,10,17,25,3,11,18,26,4,12,19,27,7,14,22,8,15,23,9,16,24,21,29,31,1,6},
  {0,4,11,18,26,29,1,8,15,23,2,9,16,24,3,10,17,25,5,12,20,6,13,21,7,14,22,19,27,30,28,31},
  {0,4,12,20,28,30,1,8,17,25,2,9,18,26,3,10,19,27,5,14,22,6,15,23,7,16,24,13,21,29,31,11},
  {0,4,11,19,28,30,1,8,16,25,2,9,17,26,3,10,18,27,5,13,22,6,14,23,7,15,24,12,21,29,31,20},
  {0,5,13,20,28,30,2,10,17,25,3,11,18,26,4,12,19,27,7,14,22,8,15,23,9,16,24,21,29,31,1,6},
  {0,4,11,18,26,29,1,8,15,23,2,9,16,24,3,10,17,25,5,12,20,6,13,21,7,14,22,19,27,30,28,31}};

struct Ring {
  uint32_t stage, phase;
  uint32_t nsig;
  __device__ __forceinline__ void next() {
    if (++stage == NSTAGE) { stage = 0; phase ^= 1; }
  }
};

struct Ctx {
  uint32_t sbase;
  uint32_t full0;
  uint32_t rel0;
  uint32_t sig;
  int cw, t;
  __device__ __forceinline__ void wait_full(const Ring& r) const { mbar_wait_fast(full0 + r.stage * 8, r.phase); }
  __device__ __forceinline__ void release(uint32_t stage) const {
    if (t < 2) mbar_arrive_cluster(rel0 + stage * 8);
  }
  __device__ __forceinline__ void release2(uint32_t s0, uint32_t s1, bool both) const {
    const uint32_t addr = rel0 + ((t & 32) ? s1 : s0) * 8;
    const uint32_t skip = t & (both ? ~33 : ~1);
    asm volatile("{\n.reg .pred p;\nsetp.eq.u32 p, %1, 0;\n@p mbarrier.arrive.shared::cluster.b64 _, [%0];\n}" ::"r"(addr), "r"(skip) : "memory");
  }
  __device__ __forceinline__ void signal(Ring& r) const {
    mbar_arrive(sig + r.nsig * 16);
    r.nsig++;
  }
  __device__ __forceinline__ void pp_sync() const { bar_sync(1 + cw, 256); }
  __device__ __forceinline__ void pp_arrive() const { bar_arrive(2 - cw, 256); }
};


template <int PAR>
__device__ __forceinline__ void xw_sub(const Ctx& c, Ring& r, uint32_t (&xa)[144], float (&acc)[64], bool last) {
  c.pp_sync();
  uint32_t prev = 0;
#pragma unroll
  for (int g = 0; g < 5; g++) {
    if (!(PAR == 1 && g == 0)) c.wait_full(r);
    const uint32_t lo = desc_lo(c.sbase + r.stage * STAGE_BYTES, 16384);
    const int sl0 = PAR ? (g == 0 ? 0 : 2 * g - 1) : 2 * g;
    const int ns = (PAR ? (g == 0) : (g == 4)) ? 1 : 2;
    const int half0 = (PAR && g == 0) ? 1 : 0;
    wg_fence();
#pragma unroll
    for (int h = 0; h < ns; h++) {
#pragma unroll
      for (int k = 0; k < 4; k++) {
        const int ai = ((sl0 + h) * 4 + k) * 4;
        wgmma_rs_n128<1>(acc, xa[ai], xa[ai + 1], xa[ai + 2], xa[ai + 3], mkdesc(lo + (((half0 + h) * 8192 + k * 2048) >> 4)), ai != 0);
      }
    }
    wg_commit();
    if (g == 2) c.pp_arrive();
    if (g > 0) { wg_wait<1>(); c.release(prev); }
    prev = r.stage;
    if (!(PAR == 0 && g == 4)) r.next();
  }
  wg_wait<0>();
  reg_fence(acc);
  if (PAR == 1) c.release(prev);
  else if (last) { c.release(prev); r.next(); }
}

__device__ __forceinline__ void xw_epi(const Ctx& c, Ring& r, const Task& tk, int mb, int sub, float (&acc)[64], float rs_lo, float rs_hi) {
  const int ub = tk.type == T_XWU ? sub : sub - tk.d, qb = tk.type == T_XWU ? sub - tk.b : sub;
  if (ub >= 0 && ub < tk.b) {
    uint4* dst = g_h + ((size_t)(mb * 288 + (tk.a + ub) * 4) * 128 + c.t);
    const float ka_lo = rs_lo * -1.4426950408889634f, ka_hi = rs_hi * -1.4426950408889634f;
    const float kb_lo = rcp(rs_lo * rs_lo), kb_hi = rcp(rs_hi * rs_hi);
#pragma unroll
    for (int i = 0; i < 4; i++) {
      float h[8];
#pragma unroll
      for (int e = 0; e < 8; e++) {
        const float ka = (e & 2) ? ka_hi : ka_lo, kb = (e & 2) ? kb_hi : kb_lo;
        const float g = acc[8 * i + e], u = acc[8 * i + e + 32];
        h[e] = (g * u) * rcp(fmaf(ex2(g * ka), kb, kb));
      }
      stg_v4(dst + i * 128, pack2(h[0], h[1]), pack2(h[2], h[3]), pack2(h[4], h[5]), pack2(h[6], h[7]));
    }
    if (ub + 1 == tk.b) c.signal(r);
  } else {
    uint4* dst = g_qo + ((size_t)(mb * 256 + (tk.c + qb) * 8) * 128 + c.t);
#pragma unroll
    for (int i = 0; i < 8; i++) {
      stg_v4(dst + i * 128, pack2(acc[8 * i] * rs_lo, acc[8 * i + 1] * rs_lo), pack2(acc[8 * i + 2] * rs_hi, acc[8 * i + 3] * rs_hi),
             pack2(acc[8 * i + 4] * rs_lo, acc[8 * i + 5] * rs_lo), pack2(acc[8 * i + 6] * rs_hi, acc[8 * i + 7] * rs_hi));
    }
    c.signal(r);
  }
}

__device__ __forceinline__ void xw_run(const Params& p, const Ctx& c, Ring& r, const Task& tk, int mb, bool first) {
  uint32_t xa[144];
  const int lane = c.t & 31, w = c.t >> 5;
  float rs_lo, rs_hi;
  {
    const uint32_t row = c.cw * 64 + w * 16 + (lane & 7) + ((lane >> 3) & 1) * 8;
    const uint32_t x7 = lane & 7, hi = lane >> 4;
    const uint32_t ONES = 0x3F803F80u;
    float s[2][4], q[4][4];
#pragma unroll
    for (int i = 0; i < 8; i++) s[i >> 2][i & 3] = 0.f;
#pragma unroll
    for (int i = 0; i < 16; i++) q[i >> 2][i & 3] = 0.f;
#pragma unroll
    for (int st = 0; st < 5; st++) {
      c.wait_full(r);
      const uint32_t sa = c.sbase + r.stage * STAGE_BYTES + row * 128;
      uint32_t dep = 0;
#pragma unroll
      for (int kk = 0; kk < (st < 4 ? 8 : 4); kk++) {
        const uint32_t addr = sa + (kk >> 2) * 16384 + (((((kk & 3) * 2) + hi) ^ x7) << 4);
        const int ai = (st * 8 + kk) * 4;
        asm volatile("ldmatrix.sync.aligned.m8n8.x4.shared.b16 {%0,%1,%2,%3}, [%4];"
                     : "=r"(xa[ai]), "=r"(xa[ai + 1]), "=r"(xa[ai + 2]), "=r"(xa[ai + 3]) : "r"(addr) : "memory");
        dep |= xa[ai];
      }
      if (st == 0 && first) asm volatile("barrier.cluster.wait.aligned;" ::: "memory");
      bar_sync(3 + c.cw + (dep & tk.e), 128);
      c.release(r.stage);
      r.next();
#pragma unroll
      for (int kk = 0; kk < (st < 4 ? 8 : 4); kk++) {
        const int ai = (st * 8 + kk) * 4;
        mma16816(s[kk & 1], xa[ai], xa[ai + 1], xa[ai + 2], xa[ai + 3], ONES, ONES);
        mma16816(q[(kk & 1) * 2], xa[ai], xa[ai + 1], xa[ai + 2], xa[ai + 3], xa[ai], xa[ai + 2]);
        mma16816(q[(kk & 1) * 2 + 1], xa[ai], xa[ai + 1], xa[ai + 2], xa[ai + 3], xa[ai + 1], xa[ai + 3]);
      }
    }
    const float mean_lo = (s[0][0] + s[1][0]) * (1.0f / DM), mean_hi = (s[0][2] + s[1][2]) * (1.0f / DM);
    const uint32_t m2_lo = pack2(mean_lo, mean_lo), m2_hi = pack2(mean_hi, mean_hi);
#pragma unroll
    for (int i = 0; i < 144; i++) asm("sub.rn.bf16x2 %0, %0, %1;" : "+r"(xa[i]) : "r"((i & 1) ? m2_hi : m2_lo));
    const int rr = lane >> 2, src = rr * 4 + (rr >> 1);
    float v_lo = __shfl_sync(0xffffffffu, (rr & 1) ? q[0][1] + q[2][1] : q[0][0] + q[2][0], src) * (1.0f / DM) - mean_lo * mean_lo;
    float v_hi = __shfl_sync(0xffffffffu, (rr & 1) ? q[1][3] + q[3][3] : q[1][2] + q[3][2], src) * (1.0f / DM) - mean_hi * mean_hi;
    if (UNLIKELY(__any_sync(0xffffffffu, !(mean_lo * mean_lo <= 64.f * v_lo && mean_hi * mean_hi <= 64.f * v_hi)))) {
      float u0[4] = {0.f, 0.f, 0.f, 0.f}, u1[4] = {0.f, 0.f, 0.f, 0.f};
#pragma unroll
      for (int i = 0; i < 36; i++) {
        mma16816(u0, xa[4 * i], xa[4 * i + 1], xa[4 * i + 2], xa[4 * i + 3], xa[4 * i], xa[4 * i + 2]);
        mma16816(u1, xa[4 * i], xa[4 * i + 1], xa[4 * i + 2], xa[4 * i + 3], xa[4 * i + 1], xa[4 * i + 3]);
      }
      const float d_lo = mean_lo - __uint_as_float(m2_lo << 16), d_hi = mean_hi - __uint_as_float(m2_hi << 16);
      v_lo = __shfl_sync(0xffffffffu, (rr & 1) ? u0[1] : u0[0], src) * (1.0f / DM) - d_lo * d_lo;
      v_hi = __shfl_sync(0xffffffffu, (rr & 1) ? u1[3] : u1[2], src) * (1.0f / DM) - d_hi * d_hi;
    }
    rs_lo = rsqrtf(fmaxf(v_lo, 0.f) + 1e-5f);
    rs_hi = rsqrtf(fmaxf(v_hi, 0.f) + 1e-5f);
  }
  const int nsub = tk.b + tk.d;
  float acc[64];
#pragma unroll
  for (int i = 0; i < 64; i++) acc[i] = 0.f;
  for (int sub = 0; sub < nsub; sub += 2) {
    xw_sub<0>(c, r, xa, acc, sub + 1 == nsub);
    xw_epi(c, r, tk, mb, sub, acc, rs_lo, rs_hi);
    if (sub + 1 < nsub) {
      xw_sub<1>(c, r, xa, acc, false);
      xw_epi(c, r, tk, mb, sub + 1, acc, rs_lo, rs_hi);
    }
  }
}

__device__ __forceinline__ void lds_frag(uint32_t (&q)[32], uint32_t addr) {
#pragma unroll
  for (int i = 0; i < 8; i++)
    asm volatile("ld.shared.v4.u32 {%0, %1, %2, %3}, [%4];" : "=r"(q[4 * i]), "=r"(q[4 * i + 1]), "=r"(q[4 * i + 2]), "=r"(q[4 * i + 3])
                 : "r"(addr + i * 2048) : "memory");
}
__device__ __forceinline__ void release_after_lds(const Ctx& c, uint32_t stage, const uint32_t (&q)[32], uint32_t zero) {
  const uint32_t dep = ((q[0] | q[4] | q[8]) | (q[12] | q[16] | q[20]) | (q[24] | q[28])) & zero;
  bar_sync(3 + c.cw + dep, 128);
  c.release(stage);
}
__device__ __forceinline__ void issue_qk(float (&s)[64], const uint32_t (&q)[32], uint32_t addr) {
  const uint32_t lo = desc_lo(addr, 16);
#pragma unroll
  for (int k = 0; k < 8; k++)
    wgmma_rs_n128<0>(s, q[4 * k], q[4 * k + 1], q[4 * k + 2], q[4 * k + 3], mkdesc(lo + (((k >> 2) * 16384 + (k & 3) * 32) >> 4)), k != 0);
  wg_commit();
}
__device__ __forceinline__ void issue_pv(float (&o)[64], const uint32_t (&pp)[32], uint32_t addr, int acc0) {
  const uint32_t lo = desc_lo(addr, 16384);
#pragma unroll
  for (int k = 0; k < 8; k++)
    wgmma_rs_n128<1>(o, pp[4 * k], pp[4 * k + 1], pp[4 * k + 2], pp[4 * k + 3], mkdesc(lo + ((k * 2048) >> 4)), k != 0 ? 1 : acc0);
  wg_commit();
}
constexpr float SM_SCALE = 0.08838834764831845f * 1.4426950408889634f;
constexpr float SM_LIMIT = 1099511627776.0f, SM_FLOOR = 1.0f / 1099511627776.0f;

template <int HALF>
__device__ __forceinline__ void exp_half(const float (&s)[64], uint32_t* pp, float c0, float c1, float (&r)[4]) {
#pragma unroll
  for (int j = 0; j < 8; j++) {
    const int b = HALF * 32 + 4 * j;
    const float e0 = ex2(fmaf(s[b], SM_SCALE, c0)), e1 = ex2(fmaf(s[b + 1], SM_SCALE, c0));
    const float e2 = ex2(fmaf(s[b + 2], SM_SCALE, c1)), e3 = ex2(fmaf(s[b + 3], SM_SCALE, c1));
    r[0] += e0; r[1] += e1; r[2] += e2; r[3] += e3;
    pp[2 * j] = pack2(e0, e1);
    pp[2 * j + 1] = pack2(e2, e3);
  }
}
__device__ __forceinline__ void tile_max(const float (&s)[64], float& n0, float& n1) {
  float a0 = fmaxf(s[0], s[1]), a1 = fmaxf(s[2], s[3]), b0 = fmaxf(s[4], s[5]), b1 = fmaxf(s[6], s[7]);
#pragma unroll
  for (int j = 2; j < 16; j += 2) {
    a0 = fmaxf(a0, fmaxf(s[4 * j], s[4 * j + 1]));
    a1 = fmaxf(a1, fmaxf(s[4 * j + 2], s[4 * j + 3]));
    b0 = fmaxf(b0, fmaxf(s[4 * j + 4], s[4 * j + 5]));
    b1 = fmaxf(b1, fmaxf(s[4 * j + 6], s[4 * j + 7]));
  }
  a0 = fmaxf(a0, b0);
  a1 = fmaxf(a1, b1);
  a0 = fmaxf(a0, __shfl_xor_sync(0xffffffffu, a0, 1));
  a1 = fmaxf(a1, __shfl_xor_sync(0xffffffffu, a1, 1));
  a0 = fmaxf(a0, __shfl_xor_sync(0xffffffffu, a0, 2));
  a1 = fmaxf(a1, __shfl_xor_sync(0xffffffffu, a1, 2));
  n0 = -a0 * SM_SCALE;
  n1 = -a1 * SM_SCALE;
}
__device__ __forceinline__ void store_o(const Ctx& c, Ring& r, const float (&o)[64], float l0, float l1, uint4* dst) {
  l0 += __shfl_xor_sync(0xffffffffu, l0, 1);
  l1 += __shfl_xor_sync(0xffffffffu, l1, 1);
  l0 += __shfl_xor_sync(0xffffffffu, l0, 2);
  l1 += __shfl_xor_sync(0xffffffffu, l1, 2);
  const float i0 = rcp(l0), i1 = rcp(l1);
#pragma unroll
  for (int i = 0; i < 8; i++)
    stg_v4(dst + i * 128, pack2(o[8 * i] * i0, o[8 * i + 1] * i0), pack2(o[8 * i + 2] * i1, o[8 * i + 3] * i1),
           pack2(o[8 * i + 4] * i0, o[8 * i + 5] * i0), pack2(o[8 * i + 6] * i1, o[8 * i + 7] * i1));
  c.signal(r);
}

template <int MODE>
__device__ __forceinline__ void att_step(const Ctx& c, Ring& r, uint32_t (&q)[32], float (&s)[64], uint32_t (&pp)[32], float (&o)[64], float& c0,
                                         float& c1, float& l0, float& l1, uint4*& qo, int acc0, uint32_t zero, int i) {
  uint32_t qst = 0;
  if (MODE != 2) {
    qst = r.stage;
    c.wait_full(r);
    r.next();
    lds_frag(q, c.sbase + qst * STAGE_BYTES + c.cw * 16384 + c.t * 16);
  }
  const uint32_t kst = r.stage;
  c.wait_full(r);
  r.next();
  uint32_t vst = 0;
  if (MODE != 0) {
    vst = r.stage;
    c.wait_full(r);
    r.next();
  }
  c.pp_sync();
  wg_fence();
  issue_qk(s, q, c.sbase + kst * STAGE_BYTES);
  if (MODE != 0) issue_pv(o, pp, c.sbase + vst * STAGE_BYTES, acc0);
  c.pp_arrive();
  if (MODE != 0) wg_wait<1>(); else wg_wait<0>();
  reg_fence(s);
  if (MODE == 0) tile_max(s, c0, c1);
  float rs[4] = {0.f, 0.f, 0.f, 0.f};
  uint32_t pt[16];
  exp_half<0>(s, pt, c0, c1, rs);
  if (MODE == 2) sched_boundary(zero);
  if (MODE == 1) sched_boundary(zero + acc0 - 1);
  if (MODE != 0) {
    wg_wait<0>();
    reg_fence(o);
    c.release2(kst, vst, true);
    if (MODE == 1) c.release(qst);
  } else {
    c.release2(kst, qst, true);
  }
  if (MODE == 1) {
    store_o(c, r, o, l0, l1, qo);
    qo += 8 * 128;
  }
#pragma unroll
  for (int e = 0; e < 16; e++) asm volatile("or.b32 %0, %1, %2;" : "=r"(pp[e]) : "r"(pt[e]), "r"(zero));
  exp_half<1>(s, pp + 16, c0, c1, rs);
  float r0 = rs[0] + rs[1], r1 = rs[2] + rs[3];
  if (MODE != 0) {
    bool bad = !(fmaxf(r0, r1) <= SM_LIMIT);
    if (MODE == 1) {
      float t0 = r0 + __shfl_xor_sync(0xffffffffu, r0, 1), t1 = r1 + __shfl_xor_sync(0xffffffffu, r1, 1);
      t0 += __shfl_xor_sync(0xffffffffu, t0, 2);
      t1 += __shfl_xor_sync(0xffffffffu, t1, 2);
      bad = bad || !(fminf(t0, t1) >= SM_FLOOR);
    }
    if (UNLIKELY(__any_sync(0xffffffffu, bad))) {
      float n0, n1;
      tile_max(s, n0, n1);
      if (MODE == 2) {
        n0 = fminf(n0, c0);
        n1 = fminf(n1, c1);
        const float al0 = ex2(n0 - c0), al1 = ex2(n1 - c1);
        l0 *= al0;
        l1 *= al1;
#pragma unroll
        for (int e = 0; e < 64; e++) o[e] *= (e & 2) ? al1 : al0;
      }
      c0 = n0;
      c1 = n1;
      float r2[4] = {0.f, 0.f, 0.f, 0.f};
      exp_half<0>(s, pp, c0, c1, r2);
      exp_half<1>(s, pp + 16, c0, c1, r2);
      r0 = r2[0] + r2[1];
      r1 = r2[2] + r2[3];
    }
  }
  if (MODE == 2) {
    l0 += r0;
    l1 += r1;
  } else {
    l0 = r0;
    l1 = r1;
  }
}

__device__ __forceinline__ void att_run(const Ctx& c, Ring& r, const Task& tk, int mb) {
  uint32_t q[32], pp[32];
  float s[64], o[64];
#pragma unroll
  for (int i = 0; i < 64; i++) { s[i] = 0.f; o[i] = 0.f; }
  uint4* qo = g_qo + ((size_t)(mb * 256 + tk.a * 8) * 128 + c.t);
  float c0 = 0.f, c1 = 0.f, l0 = 0.f, l1 = 0.f;
  att_step<0>(c, r, q, s, pp, o, c0, c1, l0, l1, qo, 0, tk.e, 0);
  for (int h = 1;; h++) {
    const bool more = h < tk.b;
    for (int j = 1; j < 16; j++) att_step<2>(c, r, q, s, pp, o, c0, c1, l0, l1, qo, j != 1, tk.e, h * 16 - 16 + j);
    if (!more) break;
    att_step<1>(c, r, q, s, pp, o, c0, c1, l0, l1, qo, 1 + tk.f, tk.e, h * 16);
  }
  c.wait_full(r);
  wg_fence();
  issue_pv(o, pp, c.sbase + r.stage * STAGE_BYTES, 1);
  wg_wait<0>();
  reg_fence(o);
  c.release(r.stage);
  r.next();
  store_o(c, r, o, l0, l1, qo);
}

template <int HALF>
__device__ __forceinline__ void proj_mma(const Ctx& c, const Ring& r, float (&acc)[96], const uint32_t (&a)[32], bool first) {
  c.wait_full(r);
  const uint32_t lo = desc_lo(c.sbase + r.stage * STAGE_BYTES, 4096);
  wg_fence();
#pragma unroll
  for (int k = 0; k < 4; k++) {
    const int ai = HALF * 16 + 4 * k;
    wgmma_rs_n192<1>(acc, a[ai], a[ai + 1], a[ai + 2], a[ai + 3], mkdesc(lo + (((k >> 1) * 12288 + (k & 1) * 2048) >> 4)), (k != 0 || HALF != 0) ? 1 : !first);
  }
  wg_commit();
}
__device__ __forceinline__ void proj_group(const Ctx& c, Ring& r, float (&acc)[96], uint32_t (&a)[32], uint32_t& prev, bool first, bool load,
                                           uint32_t zero, bool handover) {
  const uint32_t ast = r.stage;
  if (load) {
    c.wait_full(r);
    lds_frag(a, c.sbase + ast * STAGE_BYTES + c.cw * 16384 + c.t * 16);
  }
  r.next();
  proj_mma<0>(c, r, acc, a, first);
  release_after_lds(c, ast, a, zero);
  wg_wait<1>();
  if (!first) c.release(prev);
  const uint32_t b0 = r.stage;
  r.next();
  if (handover) bar_arrive(5, 256);
  proj_mma<1>(c, r, acc, a, false);
  wg_wait<1>();
  c.release(b0);
  prev = r.stage;
  r.next();
}
__device__ __forceinline__ void proj_run(const Params& p, const Ctx& c, Ring& r, const Task& tk, int mb) {
  const bool isP = tk.type == T_P;
  const int G = isP ? 32 : 36;
  float acc[96];
  uint32_t a0[32], a1[32];
#pragma unroll
  for (int i = 0; i < 96; i++) acc[i] = 0.f;
#pragma unroll
  for (int i = 0; i < 32; i++) a1[i] = 0;
  uint32_t prev = 0;
  for (int g = 0; g < G; g += 2) {
    if (!isP && g + 2 == G && c.cw == 1) bar_sync(5, 256);
    proj_group(c, r, acc, a0, prev, g == 0, true, tk.f, false);
    proj_group(c, r, acc, a1, prev, false, tk.e == 0, tk.f, !isP && g + 2 == G && c.cw == 0);
  }
  uint4* gp = g_g + ((size_t)((mb * 3 + tk.a) * 16) * 128 + c.t);
  uint32_t epoch;
  asm volatile("ld.shared.u32 %0, [%1];" : "=r"(epoch) : "r"(c.full0 + 120) : "memory");
  if (!isP) {
    wg_wait<0>();
    reg_fence(acc);
    c.release(prev);
#pragma unroll
    for (int j = 0; j < 16; j++)
      st_tagged(gp + j * 128, pack2(silu(acc[6 * j]), silu(acc[6 * j + 1])), pack2(silu(acc[6 * j + 2]), silu(acc[6 * j + 3])),
                pack2(silu(acc[6 * j + 4]), silu(acc[6 * j + 5])), epoch);
    c.signal(r);
  } else {
    const int lane = c.t & 31, w = c.t >> 5;
    const uint32_t row = c.cw * 64 + w * 16 + (lane & 7) + ((lane >> 3) & 1) * 8;
    const uint32_t x7 = lane & 7, hi = lane >> 4;
    uint32_t xv[48], g[48], sa[3];
    {
      Ring r2 = r;
      r2.next();
      c.wait_full(r2);
    }
    uint32_t tag[16], sv[48];
#pragma unroll
    for (int j = 0; j < 16; j++) ld_tagged(gp + j * 128, g[3 * j], g[3 * j + 1], g[3 * j + 2], tag[j]);
    asm volatile("wgmma.wait_group.sync.aligned 0; // final" ::: "memory");
    reg_fence(acc);
#pragma unroll
    for (int e = 0; e < 48; e++) sv[e] = pack2(acc[2 * e], acc[2 * e + 1]);
#pragma unroll
    for (int pn = 0; pn < 3; pn++) {
      if (pn != 1) {
        c.wait_full(r);
        sa[pn] = c.sbase + r.stage * STAGE_BYTES;
        r.next();
      } else {
        sa[1] = sa[0] + 16384;
      }
#pragma unroll
      for (int kk = 0; kk < 4; kk++) {
        const int e = (pn * 4 + kk) * 4;
        asm volatile("ldmatrix.sync.aligned.m8n8.x4.shared.b16 {%0,%1,%2,%3}, [%4];" : "=r"(xv[e]), "=r"(xv[e + 1]), "=r"(xv[e + 2]), "=r"(xv[e + 3])
                     : "r"(sa[pn] + row * 128 + (((kk * 2 + hi) ^ x7) << 4)) : "memory");
      }
    }
    while (true) {
      uint32_t diff = 0;
#pragma unroll
      for (int j = 0; j < 16; j++) diff |= tag[j] ^ epoch;
      if (__all_sync(0xffffffffu, diff == 0)) break;
#pragma unroll
      for (int j = 0; j < 16; j++) ld_tagged(gp + j * 128, g[3 * j], g[3 * j + 1], g[3 * j + 2], tag[j]);
    }
    c.signal(r);
    asm volatile("barrier.cluster.arrive.relaxed.aligned;" ::: "memory");
#pragma unroll
    for (int j = 0; j < 12; j++) {
#pragma unroll
      for (int e = 4 * j; e < 4 * j + 4; e++) asm("fma.rn.bf16x2 %0, %1, %2, %0;" : "+r"(xv[e]) : "r"(sv[e]), "r"(g[e]));
      asm volatile("stmatrix.sync.aligned.m8n8.x4.shared.b16 [%0], {%1,%2,%3,%4};" ::"r"(sa[j >> 2] + row * 128 + ((((j & 3) * 2 + hi) ^ x7) << 4)),
                   "r"(xv[4 * j]), "r"(xv[4 * j + 1]), "r"(xv[4 * j + 2]), "r"(xv[4 * j + 3]) : "memory");
    }
    __syncwarp();
    const uint32_t rl = c.cw * 64 + w * 16 + (lane >> 3);
    __nv_bfloat16* op = p.out + (size_t)(mb * 64 + w * 16 + (lane >> 3)) * DM + tk.a * 192 + (lane & 7) * 8;
#pragma unroll
    for (int j = 0; j < 12; j++) {
      const uint32_t rr = rl + (j & 3) * 4;
      asm volatile("ld.shared.v4.u32 {%0, %1, %2, %3}, [%4];" : "=r"(g[4 * j]), "=r"(g[4 * j + 1]), "=r"(g[4 * j + 2]), "=r"(g[4 * j + 3])
                   : "r"(sa[j >> 2] + rr * 128 + (((lane & 7) ^ (rr & 7)) << 4)) : "memory");
    }
#pragma unroll
    for (int j = 0; j < 12; j++) stg_v4(op + (j & 3) * 4 * DM + (j >> 2) * 64, g[4 * j], g[4 * j + 1], g[4 * j + 2], g[4 * j + 3]);
  }
}

__device__ __forceinline__ void load_x(const Params& p, uint32_t dst, uint32_t full, int st, int mtile) {
  if (st == 4) {
    mbar_expect(full, 16384);
    tma2d(dst, &p.tm_x, 512, mtile * 128, full);
  } else {
    mbar_expect(full, 32768);
    tma3d(dst, &p.tm_x3, 0, mtile * 128, st * 2, full);
  }
}
constexpr int TLBW = 4, GWATCH = 13;
__device__ __forceinline__ void producer(const Params& p, uint32_t sbase, uint32_t full0, uint32_t empty0, int cid, int rank) {
  Ring r{0, 1, 0};
  unsigned epoch = 0;
#define ACQ() mbar_wait(empty0 + r.stage * 8, r.phase)
#define DST (sbase + r.stage * STAGE_BYTES)
#define FULL (full0 + r.stage * 8)
#pragma unroll 1
  for (int ti = 0; ti < MAX_TASKS; ti++) {
    const Task tk = p.tasks[cid][ti];
    if (tk.type == T_END) break;
    const int mtile = tk.mp * 2 + rank;
    if ((tk.type & 3) == T_XW) {
#pragma unroll 1
      for (int st = 0; st < 5; st++) {
        if (ti > 0) {
          ACQ();
          if (elect_one()) load_x(p, DST, FULL, st, mtile);
        }
        r.next();
      }
      const int nsl = (tk.b + tk.d) * 9;
      int sub = 0, s = 0;
#pragma unroll 1
      for (int f = 0; f < nsl; f++) {
        const int h = f & 1;
        if (h == 0) ACQ();
        const int ub = tk.type == T_XWU ? sub : sub - tk.d, qb = tk.type == T_XWU ? sub - tk.b : sub;
        const bool isU = ub >= 0 && ub < tk.b;
        const CUtensorMap* tm = isU ? (rank ? &p.tm_w3 : &p.tm_w1) : &p.tm_wq;
        const int col = isU ? (tk.a + ub) * 64 : p.hperm[tk.mp][(tk.c + qb) & 31] * 128 + rank * 64;
        if (elect_one()) {
          if (h == 0) mbar_expect(FULL, f + 1 < nsl ? 32768 : 16384);
          tma2d_mc(DST + rank * 16384 + h * 8192, tm, col, s * 64, FULL);
        }
        if (++s == 9) { s = 0; sub++; }
        if (h == 1 || f + 1 == nsl) r.next();
      }
    }
    for (uint32_t n = 0; epoch == 0; n++) {
      asm volatile("ld.acquire.cta.shared.u32 %0, [%1];" : "=r"(epoch) : "r"(full0 + 120) : "memory");
      if (n > SPIN_LIMIT) asm volatile("trap;");
    }
    if ((tk.type & 3) == T_XW) {
    } else if (tk.type == T_ATT) {
      const int niter = tk.b * 16;
#pragma unroll 1
      for (int i = 0; i <= niter; i++) {
        if (i < niter) {
          const int head = tk.a + (i >> 4);
          if ((i & 15) == 0) {
            flag_wait(&g_flags[FL_Q + mtile * 32 + head], epoch);
            asm volatile("fence.proxy.async.global;" ::: "memory");
            ACQ();
            const uint4* src = g_qo + (size_t)(mtile * 2 * 256 + head * 8) * 128;
            if (elect_one()) {
              mbar_expect(FULL, 32768);
              bulk_load(DST, src, 16384, FULL);
              bulk_load(DST + 16384, src + 256 * 128, 16384, FULL);
            }
            r.next();
          }
          ACQ();
          if (elect_one()) {
            mbar_expect(FULL, 32768);
            tma2d_mc(DST + rank * 16384, &p.tm_k, rank * 64, (p.hperm[tk.mp][head] >> 1) * SEQ + (i & 15) * 128, FULL);
          }
          r.next();
        }
        if (i > 0) {
          ACQ();
          if (elect_one()) {
            mbar_expect(FULL, 32768);
            tma2d_mc(DST + rank * 16384, &p.tm_v, rank * 64, (p.hperm[tk.mp][tk.a + ((i - 1) >> 4)] >> 1) * SEQ + ((i - 1) & 15) * 128, FULL);
          }
          r.next();
        }
      }
    } else {
      const bool isP = tk.type == T_P;
      const int G = isP ? 32 : 36;
      const CUtensorMap* tm = isP ? &p.tm_wo : &p.tm_w2;
      const uint4* abase = isP ? g_qo + (size_t)mtile * 2 * 256 * 128 : g_h + (size_t)mtile * 2 * 288 * 128;
      const int astride = (isP ? 256 : 288) * 128;
      if (isP && elect_one()) {
        for (int pn = 0; pn < 3; pn++)
          asm volatile("cp.async.bulk.prefetch.tensor.2d.L2.global [%0, {%1, %2}];" ::"l"(&p.tm_x), "r"(tk.a * 192 + pn * 64), "r"(mtile * 128) : "memory");
      }
      if (!isP) {
        flag_wait(&g_flags[FL_H + mtile], 72 * epoch);
        asm volatile("fence.proxy.async.global;" ::: "memory");
      }
      const int lane = threadIdx.x & 31;
      const unsigned* oflag = &g_flags[FL_O + mtile * 32 + p.horder[tk.mp][lane]];
      uint32_t ready = 0xffffffffu;
      if (isP) {
        ready = __ballot_sync(0xffffffffu, ld_acquire(oflag) >= epoch);
        asm volatile("fence.proxy.async.global;" ::: "memory");
      }
#pragma unroll 1
      for (int g = 0; g < G; g++) {
        const int ka = isP ? p.horder[tk.mp][g] : g;
        const int kw = isP ? p.hperm[tk.mp][ka] : g;
        const Ring ra = r;
        if (g + TLBW < G && elect_one()) {
          const int gp = g + TLBW;
          const int kp = isP ? p.horder[tk.mp][gp] : gp;
          const int kq = isP ? p.hperm[tk.mp][kp] : gp;
          l2_prefetch((isP ? p.wo : p.w2) + (size_t)(kq * 128 + 127) * DM + tk.a * 192, 16);
          if ((ready >> (gp & 31)) & 1) {
            l2_prefetch(abase + kp * 1024, 16);
            l2_prefetch(abase + kp * 1024 + astride, 16);
          }
        }
        if (isP && ((~ready >> g) & 7)) {
          ready = __ballot_sync(0xffffffffu, ld_acquire(oflag) >= epoch);
          asm volatile("fence.proxy.async.global;" ::: "memory");
        }
        const bool late = !((ready >> (g & 31)) & 1);
#pragma unroll 1
        for (int pass = 0; pass < 2; pass++) {
          if ((pass == 0) != late) {
            if (late) {
              uint32_t n = 0;
              while (true) {
                ready = __ballot_sync(0xffffffffu, ld_acquire(oflag) >= epoch);
                if ((ready >> g) & 1) break;
                if (++n > SPIN_LIMIT) asm volatile("trap;");
              }
              asm volatile("fence.proxy.async.global;" ::: "memory");
            }
            r = ra;
            ACQ();
            if (elect_one()) {
              mbar_expect(FULL, 32768);
              bulk_load(DST, abase + ka * 1024, 16384, FULL);
              bulk_load(DST + 16384, abase + ka * 1024 + astride, 16384, FULL);
            }
          } else {
            r = ra;
#pragma unroll 1
            for (int h = 0; h < 2; h++) {
              r.next();
              ACQ();
              if (elect_one()) {
                mbar_expect(FULL, 24576);
                tma3d_mc(DST + rank * 12288, tm, 0, kw * 128 + h * 64 + rank * 32, tk.a * 3, FULL);
              }
            }
          }
        }
        r = ra;
        r.next();
        r.next();
        r.next();
      }
      if (isP) {
        ACQ();
        if (elect_one()) {
          mbar_expect(FULL, 32768);
          tma3d(DST, &p.tm_x3, 0, mtile * 128, tk.a * 3, FULL);
        }
        r.next();
        ACQ();
        if (elect_one()) {
          asm volatile("mbarrier.expect_tx.shared::cta.b64 [%0], 16384;" ::"r"(FULL) : "memory");
          tma2d(DST, &p.tm_x, tk.a * 192 + 128, mtile * 128, FULL);
        }
        const uint4* gw = g_g + ((size_t)(((mtile * 2 + ((lane >> 2) & 1)) * 3 + tk.a) * 16 + GWATCH) * 128 + (lane & 3) * 32);
        uint32_t n = 0;
        while (true) {
          uint32_t a, b2, c2, tag;
          ld_tagged(gw, a, b2, c2, tag);
          if (__all_sync(0xffffffffu, tag == epoch)) break;
          if (++n > SPIN_LIMIT) asm volatile("trap;");
        }
        if (elect_one()) mbar_arrive(FULL);
        r.next();
      }
    }
  }
#undef ACQ
#undef DST
#undef FULL
}

__device__ __forceinline__ void signaler(const Params& p, uint32_t sig, int cid, int rank) {
  const unsigned epoch = atomicAdd(&g_flags[FL_LAUNCH + p.last], 1) / (unsigned)p.nctas + 1;
  asm volatile("st.release.cta.shared.u32 [%0], %1;" ::"r"(sig - 8), "r"(epoch) : "memory");
  uint32_t ph = 0;
  auto publish = [&](int idx, unsigned v) {
    mbar_wait(sig + ph * 16, 0);
    mbar_wait(sig + ph * 16 + 8, 0);
    ph++;
    if (idx >= 0) {
      asm volatile("red.release.gpu.global.add.u32 [%0], %1;" ::"l"(&g_flags[idx]), "r"(v) : "memory");
    }
  };
#pragma unroll 1
  for (int ti = 0; ti < MAX_TASKS; ti++) {
    const Task tk = p.tasks[cid][ti];
    if (tk.type == T_END) break;
    const int mtile = tk.mp * 2 + rank;
    if ((tk.type & 3) == T_XW) {
      if (tk.b && tk.type == T_XWU) publish(FL_H + mtile, tk.b);
#pragma unroll 1
      for (int h = 0; h < tk.d; h++) publish(FL_Q + mtile * 32 + tk.c + h, 1);
      if (tk.b && tk.type == T_XW) publish(FL_H + mtile, tk.b);
    } else if (tk.type == T_ATT) {
#pragma unroll 1
      for (int h = 0; h < tk.b; h++) publish(FL_O + mtile * 32 + tk.a + h, 1);
    } else {
      publish(-1, 0);
    }
  }
}

__global__ void __cluster_dims__(2, 1, 1) __launch_bounds__(384, 1) mega_kernel(const __grid_constant__ Params p) {
  extern __shared__ uint8_t smem_raw[];
  const uint32_t sbase = (smem_u32(smem_raw) + 1023) & ~1023u;
  const uint32_t full0 = sbase + NSTAGE * STAGE_BYTES, empty0 = full0 + 64, sig = full0 + 128;
  uint32_t rank;
  asm("mov.u32 %0, %%cluster_ctarank;" : "=r"(rank));
  const int cid = blockIdx.x >> 1;
  const int tid = threadIdx.x;
  if (tid == 0) {
    for (int i = 0; i < NSTAGE; i++) {
      mbar_init(full0 + i * 8, 1);
      mbar_init(empty0 + i * 8, 4);
    }
    asm volatile("fence.mbarrier_init.release.cluster;" ::: "memory");
    asm volatile("fence.proxy.async.shared::cta;" ::: "memory");
    const Task tk = p.tasks[cid][0];
    if ((tk.type & 3) == T_XW) {
#pragma unroll 1
      for (int st = 0; st < 5; st++) load_x(p, sbase + st * STAGE_BYTES, full0 + st * 8, st, tk.mp * 2 + rank);
    }
  } else if (tid >= 64 && tid < 64 + 2 * NSIG) {
    mbar_init(sig + (tid - 64) * 8, 128);
  } else if (tid == 63) {
    asm volatile("st.shared.u32 [%0], 0;" ::"r"(sig - 8) : "memory");
  }
  __syncthreads();
  asm volatile("barrier.cluster.arrive.relaxed.aligned;" ::: "memory");
  const bool xw_first = (p.tasks[cid][0].type & 3) == T_XW;
  if (tid < 128) {
    asm volatile("setmaxnreg.dec.sync.aligned.u32 24;");
    const int warp = __shfl_sync(0xffffffffu, tid >> 5, 0);
    asm volatile("barrier.cluster.wait.aligned;" ::: "memory");
    if (tid >= 64 && tid < 72) asm volatile("prefetch.tensormap [%0];" ::"l"(&p.tm_k + (tid - 64)) : "memory");
    if (warp == 0) producer(p, sbase, full0, empty0, cid, rank);
    else if (tid == 32) signaler(p, sig, cid, rank);
    __syncwarp();
    cluster_sync();
  } else {
    asm volatile("setmaxnreg.inc.sync.aligned.u32 240;");
    Ring r{0, 0, 0};
    if (!xw_first) asm volatile("barrier.cluster.wait.aligned;" ::: "memory");
    if (tid >= 256) bar_arrive(1, 256);
    bool arrived = false;
    for (int ti = 0; ti < MAX_TASKS; ti++) {
      uint32_t tl;
      asm volatile("mov.u32 %0, %%tid.x;" : "=r"(tl));
      Ctx c;
      c.sbase = sbase;
      c.full0 = full0;
      c.cw = (tl >> 7) - 1;
      c.t = tl & 127;
      c.rel0 = mapa(empty0, tl & 1);
      c.sig = sig + c.cw * 8;
      const Task tk = p.tasks[cid][ti];
      if (tk.type == T_END) break;
      const int mb = (tk.mp * 2 + rank) * 2 + c.cw;
      if ((tk.type & 3) == T_XW) xw_run(p, c, r, tk, mb, ti == 0);
      else if (tk.type == T_ATT) att_run(c, r, tk, mb);
      else proj_run(p, c, r, tk, mb);
      arrived = tk.type == T_P;
    }
    if (!arrived) asm volatile("barrier.cluster.arrive.relaxed.aligned;" ::: "memory");
    asm volatile("barrier.cluster.wait.aligned;" ::: "memory");
  }
}

typedef CUresult (*EncodeFn)(CUtensorMap*, CUtensorMapDataType, cuuint32_t, void*, const cuuint64_t*, const cuuint64_t*, const cuuint32_t*,
                             const cuuint32_t*, CUtensorMapInterleave, CUtensorMapSwizzle, CUtensorMapL2promotion, CUtensorMapFloatOOBfill);

void make_map(EncodeFn fn, CUtensorMap* tm, const void* ptr, uint64_t rows, uint64_t cols, uint32_t box_rows) {
  cuuint64_t dims[2] = {cols, rows};
  cuuint64_t strides[1] = {cols * 2};
  cuuint32_t box[2] = {64, box_rows};
  cuuint32_t es[2] = {1, 1};
  fn(tm, CU_TENSOR_MAP_DATA_TYPE_BFLOAT16, 2, const_cast<void*>(ptr), dims, strides, box, es, CU_TENSOR_MAP_INTERLEAVE_NONE,
     CU_TENSOR_MAP_SWIZZLE_128B, CU_TENSOR_MAP_L2_PROMOTION_L2_128B, CU_TENSOR_MAP_FLOAT_OOB_FILL_NONE);
}

void make_map3(EncodeFn fn, CUtensorMap* tm, const void* ptr, uint64_t rows, uint64_t cols, uint32_t box_rows, uint32_t box_panels) {
  cuuint64_t dims[3] = {64, rows, cols / 64};
  cuuint64_t strides[2] = {cols * 2, 128};
  cuuint32_t box[3] = {64, box_rows, box_panels};
  cuuint32_t es[3] = {1, 1, 1};
  CUresult res = fn(tm, CU_TENSOR_MAP_DATA_TYPE_BFLOAT16, 3, const_cast<void*>(ptr), dims, strides, box, es, CU_TENSOR_MAP_INTERLEAVE_NONE,
     CU_TENSOR_MAP_SWIZZLE_128B, CU_TENSOR_MAP_L2_PROMOTION_L2_128B, CU_TENSOR_MAP_FLOAT_OOB_FILL_NONE);
  (void)res;
}

}

extern "C" void kernel_launch(void* const* d_in, const int* in_sizes, int n_in, void* d_out, int out_size) {
  static EncodeFn enc = nullptr;
  static bool resident = false;
  if (!enc) {
    void* fn = nullptr;
    cudaDriverEntryPointQueryResult qr;
    cudaGetDriverEntryPoint("cuTensorMapEncodeTiled", &fn, cudaEnableDefault, &qr);
    enc = (EncodeFn)fn;
    cudaFuncSetAttribute(mega_kernel, cudaFuncAttributeMaxDynamicSharedMemorySize, SMEM_BYTES);
    cudaLaunchConfig_t cfg = {};
    cfg.gridDim = dim3(2 * MAX_CLUSTERS);
    cfg.blockDim = dim3(384);
    cfg.dynamicSmemBytes = SMEM_BYTES;
    cudaLaunchAttribute at;
    at.id = cudaLaunchAttributeClusterDimension;
    at.val.clusterDim.x = 2;
    at.val.clusterDim.y = 1;
    at.val.clusterDim.z = 1;
    cfg.attrs = &at;
    cfg.numAttrs = 1;
    int ncl = 0;
    resident = cudaOccupancyMaxActiveClusters(&ncl, mega_kernel, &cfg) == cudaSuccess && ncl >= MAX_CLUSTERS;
    (void)cudaGetLastError();
  }
  static Params pa;
  memset(&pa, 0, sizeof(pa));
  make_map(enc, &pa.tm_x, d_in[0], SEQ, DM, 128);
  make_map3(enc, &pa.tm_x3, d_in[0], SEQ, DM, 128, 2);
  pa.out = (__nv_bfloat16*)d_out;
  pa.wo = (const __nv_bfloat16*)d_in[4];
  pa.w2 = (const __nv_bfloat16*)d_in[8];
  make_map(enc, &pa.tm_k, d_in[1], 16 * SEQ, DH, 128);
  make_map(enc, &pa.tm_v, d_in[2], 16 * SEQ, DH, 128);
  make_map(enc, &pa.tm_wq, d_in[3], DM, NH * DH, 64);
  make_map3(enc, &pa.tm_wo, d_in[4], NH * DH, DM, 32, 3);
  make_map(enc, &pa.tm_w1, d_in[6], DM, FF, 64);
  make_map(enc, &pa.tm_w3, d_in[7], DM, FF, 64);
  make_map3(enc, &pa.tm_w2, d_in[8], FF, DM, 32, 3);
  memcpy(pa.horder, HORDER, sizeof(HORDER));
  memcpy(pa.hperm, HPERM, sizeof(HPERM));
  if (resident) {
    for (int c = 0; c < MAX_CLUSTERS; c++)
      for (int i = 0; i < (int)(sizeof(SCHED[0]) / sizeof(SCHED[0][0])); i++) {
        const uint8_t* s = SCHED[c][i];
        pa.tasks[c][i] = Task{s[0], s[1], s[2], s[3], s[4], s[5], 0, 0};
      }
    pa.nctas = 2 * MAX_CLUSTERS;
    pa.last = 0;
    mega_kernel<<<pa.nctas, 384, SMEM_BYTES>>>(pa);
  } else {
    for (int ph = 0; ph < 4; ph++) {
      memset(pa.tasks, 0, sizeof(pa.tasks));
      const int ncl = ph < 2 ? 64 : 24;
      for (int c = 0; c < ncl; c++) {
        if (ph == 0) pa.tasks[c][0] = Task{T_XW, (uint8_t)(c / 8), (uint8_t)(9 * (c % 8)), 9, (uint8_t)(4 * (c % 8)), 4, 0, 0};
        if (ph == 1) pa.tasks[c][0] = Task{T_ATT, (uint8_t)(c / 8), (uint8_t)(4 * (c % 8)), 4, 0, 0, 0, 0};
        if (ph >= 2) pa.tasks[c][0] = Task{(uint8_t)(ph == 2 ? T_D : T_P), (uint8_t)(c / 3), (uint8_t)(c % 3), 0, 0, 0, 0, 0};
      }
      pa.nctas = 2 * ncl;
      pa.last = ph;
      mega_kernel<<<pa.nctas, 384, SMEM_BYTES>>>(pa);
    }
  }
}
```
